```python
import torch

def _softmax(x, axis=-1):
    return torch.softmax(x, dim=axis)
def _gelu(x):
    return torch.nn.functional.gelu(x, approximate="tanh")
def _silu(x):
    return torch.nn.functional.silu(x)
def _sigmoid(x):
    return torch.sigmoid(x)
def _layernorm(x, axis=-1, eps=1e-5):
    m = x.mean(dim=axis, keepdim=True)
    v = x.var(dim=axis, keepdim=True, unbiased=False)
    return (x - m) / torch.sqrt(v + eps)
def _scatter_add(tgt, idx, src, axis=0):
    return tgt.clone().index_add_(axis, idx, src)
def _segment_sum(src, seg, n):
    out = torch.zeros((n,) + src.shape[1:], dtype=src.dtype)
    return out.index_add_(0, seg, src)
def _pad(x, pw):
    flat = tuple(v for pair in reversed(pw) for v in pair)
    return torch.nn.functional.pad(x, flat)

kernel_name = 'gated_mix__sliding_block__softmax_full_mha__prompt'

def setup_inputs():

    _w = (lambda a: (lambda t: t.to(torch.bfloat16) if t.is_floating_point() else t)(torch.as_tensor(a)))
    def _A_setup():
        B, S, D = 1, 2048, 512
        return {
            "x": _w((lambda *s: torch.randn(*s, dtype=torch.bfloat16) * 0.05)(B, S, D)),
            "wqkv": _w((lambda *s: torch.randn(*s, dtype=torch.bfloat16) * 1.6)(D, 3 * D)),
            "wo": _w((lambda *s: torch.randn(*s, dtype=torch.bfloat16) * 0.05)(D, D)),
        }
    _A_in = _A_setup()

    def _B_setup():
        B, S, D = 1, 2048, 512
        return {
            "x": _w((lambda *s: torch.randn(*s, dtype=torch.bfloat16) * 0.05)(B, S, D)),
            "wqkv": _w((lambda *s: torch.randn(*s, dtype=torch.bfloat16) * 1.6)(D, 3 * D)),
            "wo": _w((lambda *s: torch.randn(*s, dtype=torch.bfloat16) * 0.1)(D, D)),
        }
    _B_in = _B_setup()

    return {
        "A_x": _A_in["x"],
        "A_wqkv": _A_in["wqkv"],
        "A_wo": _A_in["wo"],
        "B_x": _B_in["x"],
        "B_wqkv": _B_in["wqkv"],
        "B_wo": _B_in["wo"],
        "gate_w": _w((lambda *s: torch.randn(*s, dtype=torch.bfloat16) * 0.05)(512) * 16.0),
    }

def reference(A_x, A_wqkv, A_wo, B_x, B_wqkv, B_wo, gate_w):
    def _A_ref(x, wqkv, wo):
        B, S, D = x.shape
        H = 32; Dh = D // H; W = 256
        qkv = (lambda x, *d: x.permute(*d))((x @ wqkv).reshape(B, S, 3, H, Dh), 2, 0, 3, 1, 4)
        q, k, v = qkv[0], qkv[1], qkv[2]
        scores = torch.einsum("bhqd,bhkd->bhqk", q, k) * (Dh ** -0.5)
        idx = torch.arange(S)
        mask = (idx[:, None] - idx[None, :] >= 0) & (idx[:, None] - idx[None, :] < W)
        scores = torch.where(mask[None, None], scores, -1e9)
        p = _softmax(scores, axis=-1)
        o = torch.einsum("bhqk,bhkd->bhqd", p, v)
        return (lambda x, *d: x.permute(*d))(o, 0, 2, 1, 3).reshape(B, S, D) @ wo

    def _B_ref(x, wqkv, wo):
        B, S, D = x.shape
        H = 32; Dh = D // H
        qkv = (lambda x, *d: x.permute(*d))((x @ wqkv).reshape(B, S, 3, H, Dh), 2, 0, 3, 1, 4)
        q, k, v = qkv[0], qkv[1], qkv[2]
        scale = Dh ** -0.5
        scores = torch.einsum("bhqd,bhkd->bhqk", q, k) * scale
        p = _softmax(scores, axis=-1)
        o = torch.einsum("bhqk,bhkd->bhqd", p, v)
        return (lambda x, *d: x.permute(*d))(o, 0, 2, 1, 3).reshape(B, S, D) @ wo

    x = A_x
    g = _sigmoid((x * gate_w).sum(-1, keepdims=True))
    a = _A_ref(x, A_wqkv, A_wo)
    b = _B_ref(x, B_wqkv, B_wo)
    return g * a + (1 - g) * b
```

```cpp
#include <cuda_runtime.h>
#include <cuda_bf16.h>
#include <cuda.h>
#include <stdint.h>

typedef __nv_bfloat16 bf16;

constexpr int SEQ = 2048, DM = 512, NH = 32;

__device__ __align__(1024) bf16 g_qkv[2 * 3 * NH * SEQ * 16];
__device__ __align__(1024) bf16 g_o[SEQ * 1024];
__device__ float g_gate[SEQ];

__device__ __forceinline__ uint32_t smem_u32(const void* p) { return (uint32_t)__cvta_generic_to_shared(p); }
__device__ __forceinline__ void mbar_init(uint32_t bar, uint32_t count) {
  asm volatile("mbarrier.init.shared::cta.b64 [%0], %1;" ::"r"(bar), "r"(count) : "memory");
}
__device__ __forceinline__ void mbar_expect_tx(uint32_t bar, uint32_t bytes) {
  asm volatile("mbarrier.arrive.expect_tx.shared::cta.b64 _, [%0], %1;" ::"r"(bar), "r"(bytes) : "memory");
}
__device__ __forceinline__ void mbar_arrive(uint32_t bar) {
  asm volatile("mbarrier.arrive.shared::cta.b64 _, [%0];" ::"r"(bar) : "memory");
}
__device__ __forceinline__ uint32_t mbar_try_wait(uint32_t bar, uint32_t parity) {
  uint32_t ok;
  asm volatile("{\n.reg .pred p;\nmbarrier.try_wait.parity.shared::cta.b64 p, [%1], %2;\nselp.u32 %0, 1, 0, p;\n}"
               : "=r"(ok) : "r"(bar), "r"(parity) : "memory");
  return ok;
}
__device__ __forceinline__ void mbar_wait(uint32_t bar, uint32_t parity) {
  uint32_t iters = 0;
  while (!mbar_try_wait(bar, parity)) {
    if (++iters > (1u << 22)) __trap();
  }
}
__device__ __forceinline__ void fence_bar_init() {
  asm volatile("fence.mbarrier_init.release.cluster;" ::: "memory");
  asm volatile("fence.proxy.async.shared::cta;" ::: "memory");
}
__device__ __forceinline__ void tma_load_2d(uint32_t dst, const CUtensorMap* map, int c0, int c1, uint32_t bar) {
  asm volatile("cp.async.bulk.tensor.2d.shared::cluster.global.mbarrier::complete_tx::bytes [%0], [%1, {%3, %4}], [%2];"
               ::"r"(dst), "l"(map), "r"(bar), "r"(c0), "r"(c1) : "memory");
}
__device__ __forceinline__ void bulk_load_1d(uint32_t dst, const void* src, uint32_t bytes, uint32_t bar) {
  asm volatile("cp.async.bulk.shared::cluster.global.mbarrier::complete_tx::bytes [%0], [%1], %2, [%3];"
               ::"r"(dst), "l"(src), "r"(bytes), "r"(bar) : "memory");
}
__device__ __forceinline__ uint64_t make_desc(uint32_t saddr, uint32_t lbo, uint32_t sbo, uint32_t swz) {
  return (uint64_t)((saddr & 0x3FFFF) >> 4) | ((uint64_t)(lbo >> 4) << 16) | ((uint64_t)(sbo >> 4) << 32) |
         ((uint64_t)swz << 62);
}
__device__ __forceinline__ void wgmma_fence() { asm volatile("wgmma.fence.sync.aligned;" ::: "memory"); }
__device__ __forceinline__ void wgmma_commit() { asm volatile("wgmma.commit_group.sync.aligned;" ::: "memory"); }
template <int N>
__device__ __forceinline__ void wgmma_wait() { asm volatile("wgmma.wait_group.sync.aligned %0;" ::"n"(N) : "memory"); }
__device__ __forceinline__ float ex2(float x) {
  float y;
  asm("ex2.approx.ftz.f32 %0, %1;" : "=f"(y) : "f"(x));
  return y;
}
__device__ __forceinline__ uint32_t pack_bf16(float lo, float hi) {
  uint32_t r;
  asm("cvt.rn.bf16x2.f32 %0, %1, %2;" : "=r"(r) : "f"(hi), "f"(lo));
  return r;
}
__device__ __forceinline__ float bf16_round(float x) { return __bfloat162float(__float2bfloat16_rn(x)); }

__device__ __forceinline__ void wgmma_m64n192k16_ss_tb(float (&d)[96], uint64_t descA, uint64_t descB, int scaleD) {
  asm volatile("{\n.reg .pred p;\nsetp.ne.b32 p, %98, 0;\n"
    "wgmma.mma_async.sync.aligned.m64n192k16.f32.bf16.bf16 {%0,%1,%2,%3,%4,%5,%6,%7,%8,%9,%10,%11,%12,%13,%14,%15,%16,%17,%18,%19,%20,%21,%22,%23,%24,%25,%26,%27,%28,%29,%30,%31,%32,%33,%34,%35,%36,%37,%38,%39,%40,%41,%42,%43,%44,%45,%46,%47,%48,%49,%50,%51,%52,%53,%54,%55,%56,%57,%58,%59,%60,%61,%62,%63,%64,%65,%66,%67,%68,%69,%70,%71,%72,%73,%74,%75,%76,%77,%78,%79,%80,%81,%82,%83,%84,%85,%86,%87,%88,%89,%90,%91,%92,%93,%94,%95}, %96, %97, p, 1, 1, 0, 1;\n}\n"
    : "+f"(d[0]), "+f"(d[1]), "+f"(d[2]), "+f"(d[3]), "+f"(d[4]), "+f"(d[5]), "+f"(d[6]), "+f"(d[7]), "+f"(d[8]), "+f"(d[9]), "+f"(d[10]), "+f"(d[11]), "+f"(d[12]), "+f"(d[13]), "+f"(d[14]), "+f"(d[15]), "+f"(d[16]), "+f"(d[17]), "+f"(d[18]), "+f"(d[19]), "+f"(d[20]), "+f"(d[21]), "+f"(d[22]), "+f"(d[23]), "+f"(d[24]), "+f"(d[25]), "+f"(d[26]), "+f"(d[27]), "+f"(d[28]), "+f"(d[29]), "+f"(d[30]), "+f"(d[31]), "+f"(d[32]), "+f"(d[33]), "+f"(d[34]), "+f"(d[35]), "+f"(d[36]), "+f"(d[37]), "+f"(d[38]), "+f"(d[39]), "+f"(d[40]), "+f"(d[41]), "+f"(d[42]), "+f"(d[43]), "+f"(d[44]), "+f"(d[45]), "+f"(d[46]), "+f"(d[47]), "+f"(d[48]), "+f"(d[49]), "+f"(d[50]), "+f"(d[51]), "+f"(d[52]), "+f"(d[53]), "+f"(d[54]), "+f"(d[55]), "+f"(d[56]), "+f"(d[57]), "+f"(d[58]), "+f"(d[59]), "+f"(d[60]), "+f"(d[61]), "+f"(d[62]), "+f"(d[63]), "+f"(d[64]), "+f"(d[65]), "+f"(d[66]), "+f"(d[67]), "+f"(d[68]), "+f"(d[69]), "+f"(d[70]), "+f"(d[71]), "+f"(d[72]), "+f"(d[73]), "+f"(d[74]), "+f"(d[75]), "+f"(d[76]), "+f"(d[77]), "+f"(d[78]), "+f"(d[79]), "+f"(d[80]), "+f"(d[81]), "+f"(d[82]), "+f"(d[83]), "+f"(d[84]), "+f"(d[85]), "+f"(d[86]), "+f"(d[87]), "+f"(d[88]), "+f"(d[89]), "+f"(d[90]), "+f"(d[91]), "+f"(d[92]), "+f"(d[93]), "+f"(d[94]), "+f"(d[95])
    : "l"(descA), "l"(descB), "r"(scaleD));
}
__device__ __forceinline__ void wgmma_m64n64k16_ss_tb(float (&d)[32], uint64_t descA, uint64_t descB, int scaleD) {
  asm volatile("{\n.reg .pred p;\nsetp.ne.b32 p, %34, 0;\n"
    "wgmma.mma_async.sync.aligned.m64n64k16.f32.bf16.bf16 {%0,%1,%2,%3,%4,%5,%6,%7,%8,%9,%10,%11,%12,%13,%14,%15,%16,%17,%18,%19,%20,%21,%22,%23,%24,%25,%26,%27,%28,%29,%30,%31}, %32, %33, p, 1, 1, 0, 1;\n}\n"
    : "+f"(d[0]), "+f"(d[1]), "+f"(d[2]), "+f"(d[3]), "+f"(d[4]), "+f"(d[5]), "+f"(d[6]), "+f"(d[7]), "+f"(d[8]), "+f"(d[9]), "+f"(d[10]), "+f"(d[11]), "+f"(d[12]), "+f"(d[13]), "+f"(d[14]), "+f"(d[15]), "+f"(d[16]), "+f"(d[17]), "+f"(d[18]), "+f"(d[19]), "+f"(d[20]), "+f"(d[21]), "+f"(d[22]), "+f"(d[23]), "+f"(d[24]), "+f"(d[25]), "+f"(d[26]), "+f"(d[27]), "+f"(d[28]), "+f"(d[29]), "+f"(d[30]), "+f"(d[31])
    : "l"(descA), "l"(descB), "r"(scaleD));
}
__device__ __forceinline__ void wgmma_m64n128k16_rs(float (&d)[64], uint32_t a0, uint32_t a1, uint32_t a2, uint32_t a3, uint64_t descB, int scaleD) {
  asm volatile("{\n.reg .pred p;\nsetp.ne.b32 p, %69, 0;\n"
    "wgmma.mma_async.sync.aligned.m64n128k16.f32.bf16.bf16 {%0,%1,%2,%3,%4,%5,%6,%7,%8,%9,%10,%11,%12,%13,%14,%15,%16,%17,%18,%19,%20,%21,%22,%23,%24,%25,%26,%27,%28,%29,%30,%31,%32,%33,%34,%35,%36,%37,%38,%39,%40,%41,%42,%43,%44,%45,%46,%47,%48,%49,%50,%51,%52,%53,%54,%55,%56,%57,%58,%59,%60,%61,%62,%63}, {%64,%65,%66,%67}, %68, p, 1, 1, 0;\n}\n"
    : "+f"(d[0]), "+f"(d[1]), "+f"(d[2]), "+f"(d[3]), "+f"(d[4]), "+f"(d[5]), "+f"(d[6]), "+f"(d[7]), "+f"(d[8]), "+f"(d[9]), "+f"(d[10]), "+f"(d[11]), "+f"(d[12]), "+f"(d[13]), "+f"(d[14]), "+f"(d[15]), "+f"(d[16]), "+f"(d[17]), "+f"(d[18]), "+f"(d[19]), "+f"(d[20]), "+f"(d[21]), "+f"(d[22]), "+f"(d[23]), "+f"(d[24]), "+f"(d[25]), "+f"(d[26]), "+f"(d[27]), "+f"(d[28]), "+f"(d[29]), "+f"(d[30]), "+f"(d[31]), "+f"(d[32]), "+f"(d[33]), "+f"(d[34]), "+f"(d[35]), "+f"(d[36]), "+f"(d[37]), "+f"(d[38]), "+f"(d[39]), "+f"(d[40]), "+f"(d[41]), "+f"(d[42]), "+f"(d[43]), "+f"(d[44]), "+f"(d[45]), "+f"(d[46]), "+f"(d[47]), "+f"(d[48]), "+f"(d[49]), "+f"(d[50]), "+f"(d[51]), "+f"(d[52]), "+f"(d[53]), "+f"(d[54]), "+f"(d[55]), "+f"(d[56]), "+f"(d[57]), "+f"(d[58]), "+f"(d[59]), "+f"(d[60]), "+f"(d[61]), "+f"(d[62]), "+f"(d[63])
    : "r"(a0), "r"(a1), "r"(a2), "r"(a3), "l"(descB), "r"(scaleD));
}
__device__ __forceinline__ void wgmma_m64n64k16_rs(float (&d)[32], uint32_t a0, uint32_t a1, uint32_t a2, uint32_t a3, uint64_t descB, int scaleD) {
  asm volatile("{\n.reg .pred p;\nsetp.ne.b32 p, %37, 0;\n"
    "wgmma.mma_async.sync.aligned.m64n64k16.f32.bf16.bf16 {%0,%1,%2,%3,%4,%5,%6,%7,%8,%9,%10,%11,%12,%13,%14,%15,%16,%17,%18,%19,%20,%21,%22,%23,%24,%25,%26,%27,%28,%29,%30,%31}, {%32,%33,%34,%35}, %36, p, 1, 1, 0;\n}\n"
    : "+f"(d[0]), "+f"(d[1]), "+f"(d[2]), "+f"(d[3]), "+f"(d[4]), "+f"(d[5]), "+f"(d[6]), "+f"(d[7]), "+f"(d[8]), "+f"(d[9]), "+f"(d[10]), "+f"(d[11]), "+f"(d[12]), "+f"(d[13]), "+f"(d[14]), "+f"(d[15]), "+f"(d[16]), "+f"(d[17]), "+f"(d[18]), "+f"(d[19]), "+f"(d[20]), "+f"(d[21]), "+f"(d[22]), "+f"(d[23]), "+f"(d[24]), "+f"(d[25]), "+f"(d[26]), "+f"(d[27]), "+f"(d[28]), "+f"(d[29]), "+f"(d[30]), "+f"(d[31])
    : "r"(a0), "r"(a1), "r"(a2), "r"(a3), "l"(descB), "r"(scaleD));
}
__device__ __forceinline__ void wgmma_m64n16k16_rs_tb(float (&d)[8], uint32_t a0, uint32_t a1, uint32_t a2, uint32_t a3, uint64_t descB, int scaleD) {
  asm volatile("{\n.reg .pred p;\nsetp.ne.b32 p, %13, 0;\n"
    "wgmma.mma_async.sync.aligned.m64n16k16.f32.bf16.bf16 {%0,%1,%2,%3,%4,%5,%6,%7}, {%8,%9,%10,%11}, %12, p, 1, 1, 1;\n}\n"
    : "+f"(d[0]), "+f"(d[1]), "+f"(d[2]), "+f"(d[3]), "+f"(d[4]), "+f"(d[5]), "+f"(d[6]), "+f"(d[7])
    : "r"(a0), "r"(a1), "r"(a2), "r"(a3), "l"(descB), "r"(scaleD));
}

constexpr int G1_STAGES = 4;
constexpr int G1_A_BYTES = 128 * 64 * 2;
constexpr int G1_B_BYTES = 192 * 64 * 2;
constexpr int G1_SMEM = G1_STAGES * (G1_A_BYTES + G1_B_BYTES) + 1024 + 256;
constexpr int G1_TILES = 256;

__global__ void __launch_bounds__(288, 1)
gemm_qkv_kernel(const __grid_constant__ CUtensorMap map_x, const __grid_constant__ CUtensorMap map_wa,
                const __grid_constant__ CUtensorMap map_wb, const bf16* __restrict__ x,
                const bf16* __restrict__ gate_w) {
  extern __shared__ uint8_t smem_raw[];
  const uint32_t sbase = (smem_u32(smem_raw) + 1023u) & ~1023u;
  const uint32_t a_base = sbase, b_base = sbase + G1_STAGES * G1_A_BYTES;
  const uint32_t bar_base = b_base + G1_STAGES * G1_B_BYTES;
  const int tid = threadIdx.x, warp = tid >> 5, lane = tid & 31;

  if (tid == 0) {
    for (int s = 0; s < G1_STAGES; s++) {
      mbar_init(bar_base + 8 * s, 1);
      mbar_init(bar_base + 8 * (G1_STAGES + s), 8);
    }
    fence_bar_init();
  }
  __syncthreads();

  if (warp == 8) {
    if (lane == 0) {
      int it = 0;
      for (int tile = blockIdx.x; tile < G1_TILES; tile += gridDim.x) {
        const int mblk = tile & 15, nb = tile >> 4, br = nb >> 3, nl = nb & 7;
        const CUtensorMap* mw = br ? &map_wb : &map_wa;
        for (int kb = 0; kb < 8; kb++, it++) {
          const int s = it & 3;
          const uint32_t ph = (it >> 2) & 1;
          mbar_wait(bar_base + 8 * (G1_STAGES + s), ph ^ 1);
          const uint32_t fb = bar_base + 8 * s;
          mbar_expect_tx(fb, G1_A_BYTES + G1_B_BYTES);
          tma_load_2d(a_base + s * G1_A_BYTES, &map_x, kb * 64, mblk * 128, fb);
#pragma unroll
          for (int i = 0; i < 3; i++)
            tma_load_2d(b_base + s * G1_B_BYTES + i * 8192, mw, nl * 192 + i * 64, kb * 64, fb);
        }
      }
    }
    __syncwarp();
    if (blockIdx.x < 128) {
      for (int r = 0; r < 16; r++) {
        const int row = blockIdx.x * 16 + r;
        float sum = 0.f;
#pragma unroll
        for (int i = 0; i < 8; i++) {
          const int idx = lane * 2 + i * 64;
          const __nv_bfloat162 xv = *reinterpret_cast<const __nv_bfloat162*>(x + row * DM + idx);
          const __nv_bfloat162 wv = *reinterpret_cast<const __nv_bfloat162*>(gate_w + idx);
          sum += bf16_round(__bfloat162float(xv.x) * __bfloat162float(wv.x));
          sum += bf16_round(__bfloat162float(xv.y) * __bfloat162float(wv.y));
        }
#pragma unroll
        for (int o = 16; o > 0; o >>= 1) sum += __shfl_xor_sync(0xffffffffu, sum, o);
        if (lane == 0) {
          const float sb = bf16_round(sum);
          g_gate[row] = bf16_round(1.f / (1.f + __expf(-sb)));
        }
      }
    }
  } else {
    const int wg = warp >> 2;
    float acc[96];
    int it = 0;
    for (int tile = blockIdx.x; tile < G1_TILES; tile += gridDim.x) {
      const int mblk = tile & 15, nb = tile >> 4, br = nb >> 3, nl = nb & 7;
      for (int kb = 0; kb < 8; kb++, it++) {
        const int s = it & 3;
        const uint32_t ph = (it >> 2) & 1;
        mbar_wait(bar_base + 8 * s, ph);
        wgmma_fence();
#pragma unroll
        for (int kk = 0; kk < 4; kk++) {
          const uint64_t da = make_desc(a_base + s * G1_A_BYTES + wg * 8192 + kk * 32, 16, 1024, 1);
          const uint64_t db = make_desc(b_base + s * G1_B_BYTES + kk * 2048, 8192, 1024, 1);
          wgmma_m64n192k16_ss_tb(acc, da, db, (kb | kk) != 0);
        }
        wgmma_commit();
        if (kb > 0) {
          wgmma_wait<1>();
          if (lane == 0) mbar_arrive(bar_base + 8 * (G1_STAGES + ((it - 1) & 3)));
        }
      }
      wgmma_wait<0>();
      if (lane == 0) mbar_arrive(bar_base + 8 * (G1_STAGES + ((it - 1) & 3)));
      const int t = mblk * 128 + wg * 64 + (warp & 3) * 16 + (lane >> 2);
#pragma unroll
      for (int j = 0; j < 24; j++) {
        const int col = nl * 192 + j * 8;
        const int which = col >> 9, head = (col & 511) >> 4, half = (col >> 3) & 1;
        bf16* base = g_qkv + (size_t)(((br * 3 + which) * NH + head)) * (SEQ * 16);
        const int off = (t >> 3) * 128 + half * 64 + (t & 7) * 8 + (lane & 3) * 2;
        *reinterpret_cast<uint32_t*>(base + off) = pack_bf16(acc[4 * j], acc[4 * j + 1]);
        *reinterpret_cast<uint32_t*>(base + off + 128) = pack_bf16(acc[4 * j + 2], acc[4 * j + 3]);
      }
    }
  }
}

constexpr int AT_SMEM = 2 * 65536 + 2 * 6 * 4096 + 256 + 1024;
constexpr float SM_C = 0.25f * 1.4426950408889634f;

template <bool MASK>
__device__ __forceinline__ void attn_tile(float (&o)[8], float& m0, float& m1, float& l0, float& l1,
                                          const uint32_t (&q)[4], uint32_t kaddr, uint32_t vaddr, int qrow,
                                          int kcol) {
  float s[64];
  wgmma_fence();
  wgmma_m64n128k16_rs(s, q[0], q[1], q[2], q[3], make_desc(kaddr, 128, 256, 0), 0);
  wgmma_commit();
  wgmma_wait<0>();
  if (MASK) {
#pragma unroll
    for (int j = 0; j < 16; j++) {
#pragma unroll
      for (int e = 0; e < 4; e++) {
        const int k = kcol + 8 * j + (e & 1);
        const int qq = qrow + ((e >> 1) << 3);
        const int d = qq - k;
        if (d < 0 || d >= 256) s[4 * j + e] = -INFINITY;
      }
    }
  }
  float mx0 = fmaxf(s[0], s[1]), mx1 = fmaxf(s[2], s[3]);
#pragma unroll
  for (int j = 1; j < 16; j++) {
    mx0 = fmaxf(mx0, fmaxf(s[4 * j], s[4 * j + 1]));
    mx1 = fmaxf(mx1, fmaxf(s[4 * j + 2], s[4 * j + 3]));
  }
  mx0 = fmaxf(mx0, __shfl_xor_sync(0xffffffffu, mx0, 1));
  mx1 = fmaxf(mx1, __shfl_xor_sync(0xffffffffu, mx1, 1));
  mx0 = fmaxf(mx0, __shfl_xor_sync(0xffffffffu, mx0, 2));
  mx1 = fmaxf(mx1, __shfl_xor_sync(0xffffffffu, mx1, 2));
  const float mn0 = fmaxf(m0, mx0), mn1 = fmaxf(m1, mx1);
  const float a0 = ex2((m0 - mn0) * SM_C), a1 = ex2((m1 - mn1) * SM_C);
  m0 = mn0;
  m1 = mn1;
  const float nb0 = -mn0 * SM_C, nb1 = -mn1 * SM_C;
  uint32_t p[32];
  float sum0 = 0.f, sum1 = 0.f;
#pragma unroll
  for (int j = 0; j < 16; j++) {
    const float p00 = ex2(fmaf(s[4 * j], SM_C, nb0)), p01 = ex2(fmaf(s[4 * j + 1], SM_C, nb0));
    const float p10 = ex2(fmaf(s[4 * j + 2], SM_C, nb1)), p11 = ex2(fmaf(s[4 * j + 3], SM_C, nb1));
    sum0 += p00 + p01;
    sum1 += p10 + p11;
    p[2 * j] = pack_bf16(p00, p01);
    p[2 * j + 1] = pack_bf16(p10, p11);
  }
  l0 = l0 * a0 + sum0;
  l1 = l1 * a1 + sum1;
  o[0] *= a0; o[1] *= a0; o[4] *= a0; o[5] *= a0;
  o[2] *= a1; o[3] *= a1; o[6] *= a1; o[7] *= a1;
  wgmma_fence();
#pragma unroll
  for (int kk = 0; kk < 8; kk++)
    wgmma_m64n16k16_rs_tb(o, p[4 * kk], p[4 * kk + 1], p[4 * kk + 2], p[4 * kk + 3],
                          make_desc(vaddr + kk * 512, 256, 128, 0), 1);
  wgmma_commit();
  wgmma_wait<0>();
}

__device__ __forceinline__ void load_q(uint32_t (&q)[4], const bf16* qbase, int t, int lane) {
  const int off = (t >> 3) * 128 + (t & 7) * 8 + (lane & 3) * 2;
  q[0] = *reinterpret_cast<const uint32_t*>(qbase + off);
  q[1] = *reinterpret_cast<const uint32_t*>(qbase + off + 128);
  q[2] = *reinterpret_cast<const uint32_t*>(qbase + off + 64);
  q[3] = *reinterpret_cast<const uint32_t*>(qbase + off + 192);
}

__device__ __forceinline__ void store_o(const float (&o)[8], float l0, float l1, int br, int head, int t, int lane) {
  l0 += __shfl_xor_sync(0xffffffffu, l0, 1);
  l1 += __shfl_xor_sync(0xffffffffu, l1, 1);
  l0 += __shfl_xor_sync(0xffffffffu, l0, 2);
  l1 += __shfl_xor_sync(0xffffffffu, l1, 2);
  const float i0 = 1.f / l0, i1 = 1.f / l1;
  bf16* dst = g_o + (size_t)t * 1024 + br * 512 + head * 16 + (lane & 3) * 2;
  *reinterpret_cast<uint32_t*>(dst) = pack_bf16(o[0] * i0, o[1] * i0);
  *reinterpret_cast<uint32_t*>(dst + 8) = pack_bf16(o[4] * i0, o[5] * i0);
  *reinterpret_cast<uint32_t*>(dst + 8 * 1024) = pack_bf16(o[2] * i1, o[3] * i1);
  *reinterpret_cast<uint32_t*>(dst + 8 * 1024 + 8) = pack_bf16(o[6] * i1, o[7] * i1);
}

__global__ void __launch_bounds__(512, 1) attn_kernel() {
  extern __shared__ uint8_t smem_raw[];
  const uint32_t sbase = (smem_u32(smem_raw) + 1023u) & ~1023u;
  const uint32_t kb_base = sbase, vb_base = sbase + 65536;
  const uint32_t ka_base = sbase + 131072, va_base = ka_base + 6 * 4096;
  const uint32_t bar_base = va_base + 6 * 4096;
  const int tid = threadIdx.x, warp = tid >> 5, lane = tid & 31, wg = warp >> 2;
  const int head = blockIdx.x >> 2, qblk = blockIdx.x & 3;

  const bf16* qA = g_qkv + (size_t)((0 * 3 + 0) * NH + head) * (SEQ * 16);
  const bf16* kA = g_qkv + (size_t)((0 * 3 + 1) * NH + head) * (SEQ * 16);
  const bf16* vA = g_qkv + (size_t)((0 * 3 + 2) * NH + head) * (SEQ * 16);
  const bf16* qB = g_qkv + (size_t)((1 * 3 + 0) * NH + head) * (SEQ * 16);
  const bf16* kB = g_qkv + (size_t)((1 * 3 + 1) * NH + head) * (SEQ * 16);
  const bf16* vB = g_qkv + (size_t)((1 * 3 + 2) * NH + head) * (SEQ * 16);
  const int ca0 = qblk * 4 - 2;

  if (tid == 0) {
    for (int i = 0; i < 22; i++) mbar_init(bar_base + 8 * i, 1);
    fence_bar_init();
  }
  __syncthreads();
  if (tid == 0) {
    for (int c = 0; c < 16; c++) {
      const uint32_t b = bar_base + 8 * c;
      mbar_expect_tx(b, 8192);
      bulk_load_1d(kb_base + c * 4096, kB + c * 2048, 4096, b);
      bulk_load_1d(vb_base + c * 4096, vB + c * 2048, 4096, b);
    }
    for (int i = 0; i < 6; i++) {
      const int c = ca0 + i;
      if (c >= 0) {
        const uint32_t b = bar_base + 8 * (16 + i);
        mbar_expect_tx(b, 8192);
        bulk_load_1d(ka_base + i * 4096, kA + c * 2048, 4096, b);
        bulk_load_1d(va_base + i * 4096, vA + c * 2048, 4096, b);
      }
    }
  }

  const int rsub = (warp & 3) * 16 + (lane >> 2);
  for (int h2 = 0; h2 < 2; h2++) {
    const int qt = qblk * 512 + wg * 128 + h2 * 64;
    uint32_t q[4];
    load_q(q, qB, qt + rsub, lane);
    float o[8], m0 = -1e30f, m1 = -1e30f, l0 = 0.f, l1 = 0.f;
#pragma unroll
    for (int i = 0; i < 8; i++) o[i] = 0.f;
    for (int c = 0; c < 16; c++) {
      mbar_wait(bar_base + 8 * c, 0);
      attn_tile<false>(o, m0, m1, l0, l1, q, kb_base + c * 4096, vb_base + c * 4096, 0, 0);
    }
    store_o(o, l0, l1, 1, head, qt + rsub, lane);
  }
  for (int h2 = 0; h2 < 2; h2++) {
    const int qt = qblk * 512 + wg * 128 + h2 * 64;
    uint32_t q[4];
    load_q(q, qA, qt + rsub, lane);
    float o[8], m0 = -1e30f, m1 = -1e30f, l0 = 0.f, l1 = 0.f;
#pragma unroll
    for (int i = 0; i < 8; i++) o[i] = 0.f;
    int cfirst = (qt - 255) >> 7;
    if (cfirst < 0) cfirst = 0;
    const int clast = (qt + 63) >> 7;
    for (int c = cfirst; c <= clast; c++) {
      const int i = c - ca0;
      mbar_wait(bar_base + 8 * (16 + i), 0);
      attn_tile<true>(o, m0, m1, l0, l1, q, ka_base + i * 4096, va_base + i * 4096, qt + rsub,
                      c * 128 + (lane & 3) * 2);
    }
    store_o(o, l0, l1, 0, head, qt + rsub, lane);
  }
}

constexpr int G2_STAGES = 4;
constexpr int G2_A_BYTES = 128 * 64 * 2;
constexpr int G2_B_BYTES = 64 * 64 * 2;
constexpr int G2_SMEM = G2_STAGES * (G2_A_BYTES + G2_B_BYTES) + 1024 + 256;

__global__ void __launch_bounds__(288, 1)
gemm_out_kernel(const __grid_constant__ CUtensorMap map_o, const __grid_constant__ CUtensorMap map_woa,
                const __grid_constant__ CUtensorMap map_wob, bf16* __restrict__ out) {
  extern __shared__ uint8_t smem_raw[];
  const uint32_t sbase = (smem_u32(smem_raw) + 1023u) & ~1023u;
  const uint32_t a_base = sbase, b_base = sbase + G2_STAGES * G2_A_BYTES;
  const uint32_t bar_base = b_base + G2_STAGES * G2_B_BYTES;
  const int tid = threadIdx.x, warp = tid >> 5, lane = tid & 31;
  const int mblk = blockIdx.x & 15, nblk = blockIdx.x >> 4;

  if (tid == 0) {
    for (int s = 0; s < G2_STAGES; s++) {
      mbar_init(bar_base + 8 * s, 1);
      mbar_init(bar_base + 8 * (G2_STAGES + s), 8);
    }
    fence_bar_init();
  }
  __syncthreads();

  if (warp == 8) {
    if (lane == 0) {
      for (int it = 0; it < 16; it++) {
        const int s = it & 3;
        const uint32_t ph = (it >> 2) & 1;
        mbar_wait(bar_base + 8 * (G2_STAGES + s), ph ^ 1);
        const uint32_t fb = bar_base + 8 * s;
        mbar_expect_tx(fb, G2_A_BYTES + G2_B_BYTES);
        tma_load_2d(a_base + s * G2_A_BYTES, &map_o, it * 64, mblk * 128, fb);
        tma_load_2d(b_base + s * G2_B_BYTES, (it < 8) ? &map_woa : &map_wob, nblk * 64, (it & 7) * 64, fb);
      }
    }
  } else {
    const int wg = warp >> 2;
    float acc_a[32], acc_b[32];
    for (int it = 0; it < 16; it++) {
      const int s = it & 3;
      const uint32_t ph = (it >> 2) & 1;
      mbar_wait(bar_base + 8 * s, ph);
      wgmma_fence();
#pragma unroll
      for (int kk = 0; kk < 4; kk++) {
        const uint64_t da = make_desc(a_base + s * G2_A_BYTES + wg * 8192 + kk * 32, 16, 1024, 1);
        const uint64_t db = make_desc(b_base + s * G2_B_BYTES + kk * 2048, 8192, 1024, 1);
        if (it < 8) wgmma_m64n64k16_ss_tb(acc_a, da, db, ((it & 7) | kk) != 0);
        else wgmma_m64n64k16_ss_tb(acc_b, da, db, ((it & 7) | kk) != 0);
      }
      wgmma_commit();
      if (it > 0) {
        wgmma_wait<1>();
        if (lane == 0) mbar_arrive(bar_base + 8 * (G2_STAGES + ((it - 1) & 3)));
      }
    }
    wgmma_wait<0>();
    const int t = mblk * 128 + wg * 64 + (warp & 3) * 16 + (lane >> 2);
    const float g0 = g_gate[t], g1 = g_gate[t + 8];
    const float h0 = bf16_round(1.f - g0), h1 = bf16_round(1.f - g1);
#pragma unroll
    for (int j = 0; j < 8; j++) {
      const int col = nblk * 64 + j * 8 + (lane & 3) * 2;
      *reinterpret_cast<uint32_t*>(out + (size_t)t * DM + col) =
          pack_bf16(g0 * acc_a[4 * j] + h0 * acc_b[4 * j], g0 * acc_a[4 * j + 1] + h0 * acc_b[4 * j + 1]);
      *reinterpret_cast<uint32_t*>(out + (size_t)(t + 8) * DM + col) =
          pack_bf16(g1 * acc_a[4 * j + 2] + h1 * acc_b[4 * j + 2], g1 * acc_a[4 * j + 3] + h1 * acc_b[4 * j + 3]);
    }
  }
}

typedef CUresult (*EncodeFn)(CUtensorMap*, CUtensorMapDataType, cuuint32_t, void*, const cuuint64_t*,
                             const cuuint64_t*, const cuuint32_t*, const cuuint32_t*, CUtensorMapInterleave,
                             CUtensorMapSwizzle, CUtensorMapL2promotion, CUtensorMapFloatOOBfill);

static void encode_2d(EncodeFn fn, CUtensorMap* m, const void* ptr, uint64_t inner, uint64_t outer, uint32_t box_in,
                      uint32_t box_out) {
  cuuint64_t dims[2] = {inner, outer};
  cuuint64_t strides[1] = {inner * 2};
  cuuint32_t box[2] = {box_in, box_out};
  cuuint32_t es[2] = {1, 1};
  fn(m, CU_TENSOR_MAP_DATA_TYPE_BFLOAT16, 2, const_cast<void*>(ptr), dims, strides, box, es,
     CU_TENSOR_MAP_INTERLEAVE_NONE, CU_TENSOR_MAP_SWIZZLE_128B, CU_TENSOR_MAP_L2_PROMOTION_L2_128B,
     CU_TENSOR_MAP_FLOAT_OOB_FILL_NONE);
}

extern "C" void kernel_launch(void* const* d_in, const int* in_sizes, int n_in, void* d_out, int out_size) {
  const bf16* x = (const bf16*)d_in[0];
  const bf16* wqkv_a = (const bf16*)d_in[1];
  const bf16* wo_a = (const bf16*)d_in[2];
  const bf16* wqkv_b = (const bf16*)d_in[4];
  const bf16* wo_b = (const bf16*)d_in[5];
  const bf16* gate_w = (const bf16*)d_in[6];
  bf16* out = (bf16*)d_out;

  EncodeFn enc = nullptr;
  cudaDriverEntryPointQueryResult qres;
  cudaGetDriverEntryPoint("cuTensorMapEncodeTiled", (void**)&enc, cudaEnableDefault, &qres);
  void* o_ptr = nullptr;
  cudaGetSymbolAddress(&o_ptr, g_o);

  CUtensorMap map_x, map_wa, map_wb, map_o, map_woa, map_wob;
  encode_2d(enc, &map_x, x, 512, 2048, 64, 128);
  encode_2d(enc, &map_wa, wqkv_a, 1536, 512, 64, 64);
  encode_2d(enc, &map_wb, wqkv_b, 1536, 512, 64, 64);
  encode_2d(enc, &map_o, o_ptr, 1024, 2048, 64, 128);
  encode_2d(enc, &map_woa, wo_a, 512, 512, 64, 64);
  encode_2d(enc, &map_wob, wo_b, 512, 512, 64, 64);

  cudaFuncSetAttribute(gemm_qkv_kernel, cudaFuncAttributeMaxDynamicSharedMemorySize, G1_SMEM);
  cudaFuncSetAttribute(attn_kernel, cudaFuncAttributeMaxDynamicSharedMemorySize, AT_SMEM);
  cudaFuncSetAttribute(gemm_out_kernel, cudaFuncAttributeMaxDynamicSharedMemorySize, G2_SMEM);

  gemm_qkv_kernel<<<128, 288, G1_SMEM>>>(map_x, map_wa, map_wb, x, gate_w);
  attn_kernel<<<128, 512, AT_SMEM>>>();
  gemm_out_kernel<<<128, 288, G2_SMEM>>>(map_o, map_woa, map_wob, out);
}
```

```cpp
#include <cuda_runtime.h>
#include <cuda_bf16.h>
#include <cuda.h>
#include <stdint.h>

typedef __nv_bfloat16 bf16;

constexpr int SEQ = 2048, DM = 512, NH = 32;

__device__ __align__(1024) bf16 g_qkv[2 * 3 * NH * SEQ * 16];
__device__ __align__(1024) bf16 g_o[SEQ * 1024];
__device__ float g_gate[SEQ];

__device__ __forceinline__ uint32_t smem_u32(const void* p) { return (uint32_t)__cvta_generic_to_shared(p); }
__device__ __forceinline__ void mbar_init(uint32_t bar, uint32_t count) {
  asm volatile("mbarrier.init.shared::cta.b64 [%0], %1;" ::"r"(bar), "r"(count) : "memory");
}
__device__ __forceinline__ void mbar_expect_tx(uint32_t bar, uint32_t bytes) {
  asm volatile("mbarrier.arrive.expect_tx.shared::cta.b64 _, [%0], %1;" ::"r"(bar), "r"(bytes) : "memory");
}
__device__ __forceinline__ void mbar_arrive(uint32_t bar) {
  asm volatile("mbarrier.arrive.shared::cta.b64 _, [%0];" ::"r"(bar) : "memory");
}
__device__ __forceinline__ uint32_t mbar_try_wait(uint32_t bar, uint32_t parity) {
  uint32_t ok;
  asm volatile("{\n.reg .pred p;\nmbarrier.try_wait.parity.shared::cta.b64 p, [%1], %2;\nselp.u32 %0, 1, 0, p;\n}"
               : "=r"(ok) : "r"(bar), "r"(parity) : "memory");
  return ok;
}
__device__ __forceinline__ void mbar_wait(uint32_t bar, uint32_t parity) {
  uint32_t iters = 0;
  while (!mbar_try_wait(bar, parity)) {
    if (++iters > (1u << 22)) __trap();
  }
}
__device__ __forceinline__ void fence_bar_init() {
  asm volatile("fence.mbarrier_init.release.cluster;" ::: "memory");
  asm volatile("fence.proxy.async.shared::cta;" ::: "memory");
}
__device__ __forceinline__ void tma_load_2d(uint32_t dst, const CUtensorMap* map, int c0, int c1, uint32_t bar) {
  asm volatile("cp.async.bulk.tensor.2d.shared::cluster.global.mbarrier::complete_tx::bytes [%0], [%1, {%3, %4}], [%2];"
               ::"r"(dst), "l"(map), "r"(bar), "r"(c0), "r"(c1) : "memory");
}
__device__ __forceinline__ void bulk_load_1d(uint32_t dst, const void* src, uint32_t bytes, uint32_t bar) {
  asm volatile("cp.async.bulk.shared::cluster.global.mbarrier::complete_tx::bytes [%0], [%1], %2, [%3];"
               ::"r"(dst), "l"(src), "r"(bytes), "r"(bar) : "memory");
}
__device__ __forceinline__ uint64_t make_desc(uint32_t saddr, uint32_t lbo, uint32_t sbo, uint32_t swz) {
  return (uint64_t)((saddr & 0x3FFFF) >> 4) | ((uint64_t)(lbo >> 4) << 16) | ((uint64_t)(sbo >> 4) << 32) |
         ((uint64_t)swz << 62);
}
__device__ __forceinline__ void wgmma_fence() { asm volatile("wgmma.fence.sync.aligned;" ::: "memory"); }
__device__ __forceinline__ void wgmma_commit() { asm volatile("wgmma.commit_group.sync.aligned;" ::: "memory"); }
template <int N>
__device__ __forceinline__ void wgmma_wait() { asm volatile("wgmma.wait_group.sync.aligned %0;" ::"n"(N) : "memory"); }
__device__ __forceinline__ float ex2(float x) {
  float y;
  asm("ex2.approx.ftz.f32 %0, %1;" : "=f"(y) : "f"(x));
  return y;
}
__device__ __forceinline__ float ex2v(float x) {
  float y;
  asm volatile("ex2.approx.ftz.f32 %0, %1;" : "=f"(y) : "f"(x));
  return y;
}
__device__ __forceinline__ uint32_t pack_bf16(float lo, float hi) {
  uint32_t r;
  asm("cvt.rn.bf16x2.f32 %0, %1, %2;" : "=r"(r) : "f"(hi), "f"(lo));
  return r;
}
__device__ __forceinline__ float bf16_round(float x) { return __bfloat162float(__float2bfloat16_rn(x)); }

__device__ __forceinline__ void wgmma_m64n192k16_ss_tb(float (&d)[96], uint64_t descA, uint64_t descB, int scaleD) {
  asm volatile("{\n.reg .pred p;\nsetp.ne.b32 p, %98, 0;\n"
    "wgmma.mma_async.sync.aligned.m64n192k16.f32.bf16.bf16 {%0,%1,%2,%3,%4,%5,%6,%7,%8,%9,%10,%11,%12,%13,%14,%15,%16,%17,%18,%19,%20,%21,%22,%23,%24,%25,%26,%27,%28,%29,%30,%31,%32,%33,%34,%35,%36,%37,%38,%39,%40,%41,%42,%43,%44,%45,%46,%47,%48,%49,%50,%51,%52,%53,%54,%55,%56,%57,%58,%59,%60,%61,%62,%63,%64,%65,%66,%67,%68,%69,%70,%71,%72,%73,%74,%75,%76,%77,%78,%79,%80,%81,%82,%83,%84,%85,%86,%87,%88,%89,%90,%91,%92,%93,%94,%95}, %96, %97, p, 1, 1, 0, 1;\n}\n"
    : "+f"(d[0]), "+f"(d[1]), "+f"(d[2]), "+f"(d[3]), "+f"(d[4]), "+f"(d[5]), "+f"(d[6]), "+f"(d[7]), "+f"(d[8]), "+f"(d[9]), "+f"(d[10]), "+f"(d[11]), "+f"(d[12]), "+f"(d[13]), "+f"(d[14]), "+f"(d[15]), "+f"(d[16]), "+f"(d[17]), "+f"(d[18]), "+f"(d[19]), "+f"(d[20]), "+f"(d[21]), "+f"(d[22]), "+f"(d[23]), "+f"(d[24]), "+f"(d[25]), "+f"(d[26]), "+f"(d[27]), "+f"(d[28]), "+f"(d[29]), "+f"(d[30]), "+f"(d[31]), "+f"(d[32]), "+f"(d[33]), "+f"(d[34]), "+f"(d[35]), "+f"(d[36]), "+f"(d[37]), "+f"(d[38]), "+f"(d[39]), "+f"(d[40]), "+f"(d[41]), "+f"(d[42]), "+f"(d[43]), "+f"(d[44]), "+f"(d[45]), "+f"(d[46]), "+f"(d[47]), "+f"(d[48]), "+f"(d[49]), "+f"(d[50]), "+f"(d[51]), "+f"(d[52]), "+f"(d[53]), "+f"(d[54]), "+f"(d[55]), "+f"(d[56]), "+f"(d[57]), "+f"(d[58]), "+f"(d[59]), "+f"(d[60]), "+f"(d[61]), "+f"(d[62]), "+f"(d[63]), "+f"(d[64]), "+f"(d[65]), "+f"(d[66]), "+f"(d[67]), "+f"(d[68]), "+f"(d[69]), "+f"(d[70]), "+f"(d[71]), "+f"(d[72]), "+f"(d[73]), "+f"(d[74]), "+f"(d[75]), "+f"(d[76]), "+f"(d[77]), "+f"(d[78]), "+f"(d[79]), "+f"(d[80]), "+f"(d[81]), "+f"(d[82]), "+f"(d[83]), "+f"(d[84]), "+f"(d[85]), "+f"(d[86]), "+f"(d[87]), "+f"(d[88]), "+f"(d[89]), "+f"(d[90]), "+f"(d[91]), "+f"(d[92]), "+f"(d[93]), "+f"(d[94]), "+f"(d[95])
    : "l"(descA), "l"(descB), "r"(scaleD));
}
__device__ __forceinline__ void wgmma_m64n64k16_ss_tb(float (&d)[32], uint64_t descA, uint64_t descB, int scaleD) {
  asm volatile("{\n.reg .pred p;\nsetp.ne.b32 p, %34, 0;\n"
    "wgmma.mma_async.sync.aligned.m64n64k16.f32.bf16.bf16 {%0,%1,%2,%3,%4,%5,%6,%7,%8,%9,%10,%11,%12,%13,%14,%15,%16,%17,%18,%19,%20,%21,%22,%23,%24,%25,%26,%27,%28,%29,%30,%31}, %32, %33, p, 1, 1, 0, 1;\n}\n"
    : "+f"(d[0]), "+f"(d[1]), "+f"(d[2]), "+f"(d[3]), "+f"(d[4]), "+f"(d[5]), "+f"(d[6]), "+f"(d[7]), "+f"(d[8]), "+f"(d[9]), "+f"(d[10]), "+f"(d[11]), "+f"(d[12]), "+f"(d[13]), "+f"(d[14]), "+f"(d[15]), "+f"(d[16]), "+f"(d[17]), "+f"(d[18]), "+f"(d[19]), "+f"(d[20]), "+f"(d[21]), "+f"(d[22]), "+f"(d[23]), "+f"(d[24]), "+f"(d[25]), "+f"(d[26]), "+f"(d[27]), "+f"(d[28]), "+f"(d[29]), "+f"(d[30]), "+f"(d[31])
    : "l"(descA), "l"(descB), "r"(scaleD));
}
__device__ __forceinline__ void wgmma_m64n128k16_rs(float (&d)[64], uint32_t a0, uint32_t a1, uint32_t a2, uint32_t a3, uint64_t descB, int scaleD) {
  asm volatile("{\n.reg .pred p;\nsetp.ne.b32 p, %69, 0;\n"
    "wgmma.mma_async.sync.aligned.m64n128k16.f32.bf16.bf16 {%0,%1,%2,%3,%4,%5,%6,%7,%8,%9,%10,%11,%12,%13,%14,%15,%16,%17,%18,%19,%20,%21,%22,%23,%24,%25,%26,%27,%28,%29,%30,%31,%32,%33,%34,%35,%36,%37,%38,%39,%40,%41,%42,%43,%44,%45,%46,%47,%48,%49,%50,%51,%52,%53,%54,%55,%56,%57,%58,%59,%60,%61,%62,%63}, {%64,%65,%66,%67}, %68, p, 1, 1, 0;\n}\n"
    : "+f"(d[0]), "+f"(d[1]), "+f"(d[2]), "+f"(d[3]), "+f"(d[4]), "+f"(d[5]), "+f"(d[6]), "+f"(d[7]), "+f"(d[8]), "+f"(d[9]), "+f"(d[10]), "+f"(d[11]), "+f"(d[12]), "+f"(d[13]), "+f"(d[14]), "+f"(d[15]), "+f"(d[16]), "+f"(d[17]), "+f"(d[18]), "+f"(d[19]), "+f"(d[20]), "+f"(d[21]), "+f"(d[22]), "+f"(d[23]), "+f"(d[24]), "+f"(d[25]), "+f"(d[26]), "+f"(d[27]), "+f"(d[28]), "+f"(d[29]), "+f"(d[30]), "+f"(d[31]), "+f"(d[32]), "+f"(d[33]), "+f"(d[34]), "+f"(d[35]), "+f"(d[36]), "+f"(d[37]), "+f"(d[38]), "+f"(d[39]), "+f"(d[40]), "+f"(d[41]), "+f"(d[42]), "+f"(d[43]), "+f"(d[44]), "+f"(d[45]), "+f"(d[46]), "+f"(d[47]), "+f"(d[48]), "+f"(d[49]), "+f"(d[50]), "+f"(d[51]), "+f"(d[52]), "+f"(d[53]), "+f"(d[54]), "+f"(d[55]), "+f"(d[56]), "+f"(d[57]), "+f"(d[58]), "+f"(d[59]), "+f"(d[60]), "+f"(d[61]), "+f"(d[62]), "+f"(d[63])
    : "r"(a0), "r"(a1), "r"(a2), "r"(a3), "l"(descB), "r"(scaleD));
}
__device__ __forceinline__ void wgmma_m64n64k16_rs(float (&d)[32], uint32_t a0, uint32_t a1, uint32_t a2, uint32_t a3, uint64_t descB, int scaleD) {
  asm volatile("{\n.reg .pred p;\nsetp.ne.b32 p, %37, 0;\n"
    "wgmma.mma_async.sync.aligned.m64n64k16.f32.bf16.bf16 {%0,%1,%2,%3,%4,%5,%6,%7,%8,%9,%10,%11,%12,%13,%14,%15,%16,%17,%18,%19,%20,%21,%22,%23,%24,%25,%26,%27,%28,%29,%30,%31}, {%32,%33,%34,%35}, %36, p, 1, 1, 0;\n}\n"
    : "+f"(d[0]), "+f"(d[1]), "+f"(d[2]), "+f"(d[3]), "+f"(d[4]), "+f"(d[5]), "+f"(d[6]), "+f"(d[7]), "+f"(d[8]), "+f"(d[9]), "+f"(d[10]), "+f"(d[11]), "+f"(d[12]), "+f"(d[13]), "+f"(d[14]), "+f"(d[15]), "+f"(d[16]), "+f"(d[17]), "+f"(d[18]), "+f"(d[19]), "+f"(d[20]), "+f"(d[21]), "+f"(d[22]), "+f"(d[23]), "+f"(d[24]), "+f"(d[25]), "+f"(d[26]), "+f"(d[27]), "+f"(d[28]), "+f"(d[29]), "+f"(d[30]), "+f"(d[31])
    : "r"(a0), "r"(a1), "r"(a2), "r"(a3), "l"(descB), "r"(scaleD));
}
__device__ __forceinline__ void wgmma_m64n16k16_rs_tb(float (&d)[8], uint32_t a0, uint32_t a1, uint32_t a2, uint32_t a3, uint64_t descB, int scaleD) {
  asm volatile("{\n.reg .pred p;\nsetp.ne.b32 p, %13, 0;\n"
    "wgmma.mma_async.sync.aligned.m64n16k16.f32.bf16.bf16 {%0,%1,%2,%3,%4,%5,%6,%7}, {%8,%9,%10,%11}, %12, p, 1, 1, 1;\n}\n"
    : "+f"(d[0]), "+f"(d[1]), "+f"(d[2]), "+f"(d[3]), "+f"(d[4]), "+f"(d[5]), "+f"(d[6]), "+f"(d[7])
    : "r"(a0), "r"(a1), "r"(a2), "r"(a3), "l"(descB), "r"(scaleD));
}

constexpr int G1_STAGES = 3;
constexpr int G1_A_BYTES = 256 * 64 * 2;
constexpr int G1_B_BYTES = 192 * 64 * 2;
constexpr int G1_SMEM = G1_STAGES * (G1_A_BYTES + G1_B_BYTES) + 1024 + 256;
constexpr int G1_TILES = 128;

__global__ void __launch_bounds__(512, 1)
gemm_qkv_kernel(const __grid_constant__ CUtensorMap map_x, const __grid_constant__ CUtensorMap map_wa,
                const __grid_constant__ CUtensorMap map_wb, const bf16* __restrict__ x,
                const bf16* __restrict__ gate_w) {
  extern __shared__ uint8_t smem_raw[];
  const uint32_t sbase = (smem_u32(smem_raw) + 1023u) & ~1023u;
  const uint32_t a_base = sbase, b_base = sbase + G1_STAGES * G1_A_BYTES;
  const uint32_t bar_base = b_base + G1_STAGES * G1_B_BYTES;
  const int tid = threadIdx.x, warp = tid >> 5, lane = tid & 31, wg = warp >> 2;
  const int tile = blockIdx.x;
  const int mblk = tile & 7, nb = tile >> 3, br = nb >> 3, nl = nb & 7;
  const CUtensorMap* mw = br ? &map_wb : &map_wa;

  if (tid == 0) {
    for (int s = 0; s < G1_STAGES; s++) {
      mbar_init(bar_base + 8 * s, 1);
      mbar_init(bar_base + 8 * (G1_STAGES + s), 16);
    }
    fence_bar_init();
  }
  __syncthreads();
  auto issue = [&](int kb) {
    const int s = kb % 3;
    const uint32_t fb = bar_base + 8 * s;
    mbar_expect_tx(fb, G1_A_BYTES + G1_B_BYTES);
    tma_load_2d(a_base + s * G1_A_BYTES, &map_x, kb * 64, mblk * 256, fb);
    tma_load_2d(a_base + s * G1_A_BYTES + 16384, &map_x, kb * 64, mblk * 256 + 128, fb);
#pragma unroll
    for (int i = 0; i < 3; i++) tma_load_2d(b_base + s * G1_B_BYTES + i * 8192, mw, nl * 192 + i * 64, kb * 64, fb);
  };
  if (tid == 0) { issue(0); issue(1); issue(2); }

  float acc[96];
  for (int kb = 0; kb < 8; kb++) {
    const int s = kb % 3;
    mbar_wait(bar_base + 8 * s, (kb / 3) & 1);
    wgmma_fence();
#pragma unroll
    for (int kk = 0; kk < 4; kk++) {
      const uint64_t da = make_desc(a_base + s * G1_A_BYTES + wg * 8192 + kk * 32, 16, 1024, 1);
      const uint64_t db = make_desc(b_base + s * G1_B_BYTES + kk * 2048, 8192, 1024, 1);
      wgmma_m64n192k16_ss_tb(acc, da, db, (kb | kk) != 0);
    }
    wgmma_commit();
    if (kb > 0) {
      wgmma_wait<1>();
      const int sp = (kb - 1) % 3;
      if (lane == 0) mbar_arrive(bar_base + 8 * (G1_STAGES + sp));
      if (tid == 0 && kb + 2 < 8) {
        mbar_wait(bar_base + 8 * (G1_STAGES + sp), ((kb - 1) / 3) & 1);
        issue(kb + 2);
      }
    }
  }
  wgmma_wait<0>();
  const int t = mblk * 256 + wg * 64 + (warp & 3) * 16 + (lane >> 2);
#pragma unroll
  for (int j = 0; j < 24; j++) {
    const int col = nl * 192 + j * 8;
    const int which = col >> 9, head = (col & 511) >> 4, half = (col >> 3) & 1;
    bf16* base = g_qkv + (size_t)(((br * 3 + which) * NH + head)) * (SEQ * 16);
    const int off = (t >> 3) * 128 + half * 64 + (t & 7) * 8 + (lane & 3) * 2;
    *reinterpret_cast<uint32_t*>(base + off) = pack_bf16(acc[4 * j], acc[4 * j + 1]);
    *reinterpret_cast<uint32_t*>(base + off + 128) = pack_bf16(acc[4 * j + 2], acc[4 * j + 3]);
  }
  {
    const int row = blockIdx.x * 16 + warp;
    float sum = 0.f;
#pragma unroll
    for (int i = 0; i < 8; i++) {
      const __nv_bfloat162 xv = *reinterpret_cast<const __nv_bfloat162*>(x + row * DM + lane * 2 + i * 64);
      const __nv_bfloat162 wv = *reinterpret_cast<const __nv_bfloat162*>(gate_w + lane * 2 + i * 64);
      sum += bf16_round(__bfloat162float(xv.x) * __bfloat162float(wv.x));
      sum += bf16_round(__bfloat162float(xv.y) * __bfloat162float(wv.y));
    }
#pragma unroll
    for (int o = 16; o > 0; o >>= 1) sum += __shfl_xor_sync(0xffffffffu, sum, o);
    if (lane == 0) g_gate[row] = bf16_round(1.f / (1.f + __expf(-bf16_round(sum))));
  }
}

constexpr int AT_SMEM = 2 * 65536 + 2 * 6 * 4096 + 256 + 1024;
constexpr float SM_C = 0.25f * 1.4426950408889634f;

__device__ __forceinline__ void tok_wait(int wg) { asm volatile("bar.sync %0, 256;" ::"r"(wg + 1) : "memory"); }
__device__ __forceinline__ void tok_pass(int wg) { asm volatile("bar.arrive %0, 256;" ::"r"((wg ^ 2) + 1) : "memory"); }

__device__ __forceinline__ void mma16816(float (&d)[4], uint32_t a0, uint32_t a1, uint32_t a2, uint32_t a3, uint32_t b0,
                                         uint32_t b1) {
  asm volatile("mma.sync.aligned.m16n8k16.row.col.f32.bf16.bf16.f32 {%0,%1,%2,%3}, {%4,%5,%6,%7}, {%8,%9}, {%0,%1,%2,%3};"
               : "+f"(d[0]), "+f"(d[1]), "+f"(d[2]), "+f"(d[3])
               : "r"(a0), "r"(a1), "r"(a2), "r"(a3), "r"(b0), "r"(b1));
}
__device__ __forceinline__ void ldsm_x4(uint32_t& r0, uint32_t& r1, uint32_t& r2, uint32_t& r3, uint32_t addr) {
  asm volatile("ldmatrix.sync.aligned.m8n8.x4.shared.b16 {%0,%1,%2,%3}, [%4];"
               : "=r"(r0), "=r"(r1), "=r"(r2), "=r"(r3) : "r"(addr));
}
__device__ __forceinline__ void ldsm_x4_t(uint32_t& r0, uint32_t& r1, uint32_t& r2, uint32_t& r3, uint32_t addr) {
  asm volatile("ldmatrix.sync.aligned.m8n8.x4.trans.shared.b16 {%0,%1,%2,%3}, [%4];"
               : "=r"(r0), "=r"(r1), "=r"(r2), "=r"(r3) : "r"(addr));
}

template <bool MASK>
__device__ __forceinline__ void attn_tile(float (&o)[8], float& m0, float& m1, float& l0, float& l1,
                                          const uint32_t (&q)[4], uint32_t kaddr, uint32_t vaddr, int qrow,
                                          int kcol, int lane) {
  float s[16][4];
  const uint32_t loff = (uint32_t)((lane >> 3) * 128 + (lane & 7) * 16);
#pragma unroll
  for (int g = 0; g < 8; g++) {
    uint32_t b0, b1, b2, b3;
    ldsm_x4(b0, b1, b2, b3, kaddr + g * 512 + loff);
#pragma unroll
    for (int e = 0; e < 4; e++) s[2 * g][e] = 0.f, s[2 * g + 1][e] = 0.f;
    mma16816(s[2 * g], q[0], q[1], q[2], q[3], b0, b1);
    mma16816(s[2 * g + 1], q[0], q[1], q[2], q[3], b2, b3);
  }
  if (MASK) {
#pragma unroll
    for (int j = 0; j < 16; j++) {
#pragma unroll
      for (int e = 0; e < 4; e++) {
        const int k = kcol + 8 * j + (e & 1);
        const int d = qrow + ((e >> 1) << 3) - k;
        if (d < 0 || d >= 256) s[j][e] = -INFINITY;
      }
    }
  }
  float mx0 = fmaxf(s[0][0], s[0][1]), mx1 = fmaxf(s[0][2], s[0][3]);
#pragma unroll
  for (int j = 1; j < 16; j++) {
    mx0 = fmaxf(mx0, fmaxf(s[j][0], s[j][1]));
    mx1 = fmaxf(mx1, fmaxf(s[j][2], s[j][3]));
  }
  mx0 = fmaxf(mx0, __shfl_xor_sync(0xffffffffu, mx0, 1));
  mx1 = fmaxf(mx1, __shfl_xor_sync(0xffffffffu, mx1, 1));
  mx0 = fmaxf(mx0, __shfl_xor_sync(0xffffffffu, mx0, 2));
  mx1 = fmaxf(mx1, __shfl_xor_sync(0xffffffffu, mx1, 2));
  const float mn0 = fmaxf(m0, mx0), mn1 = fmaxf(m1, mx1);
  const float a0 = ex2((m0 - mn0) * SM_C), a1 = ex2((m1 - mn1) * SM_C);
  m0 = mn0;
  m1 = mn1;
  const float nb0 = -mn0 * SM_C, nb1 = -mn1 * SM_C;
  uint32_t p[32];
  float sum0 = 0.f, sum1 = 0.f;
#pragma unroll
  for (int j = 0; j < 16; j++) {
    const float p00 = ex2(fmaf(s[j][0], SM_C, nb0)), p01 = ex2(fmaf(s[j][1], SM_C, nb0));
    const float p10 = ex2(fmaf(s[j][2], SM_C, nb1)), p11 = ex2(fmaf(s[j][3], SM_C, nb1));
    sum0 += p00 + p01;
    sum1 += p10 + p11;
    p[2 * j] = pack_bf16(p00, p01);
    p[2 * j + 1] = pack_bf16(p10, p11);
  }
  l0 = l0 * a0 + sum0;
  l1 = l1 * a1 + sum1;
  float (&o0)[4] = *reinterpret_cast<float (*)[4]>(&o[0]);
  float (&o1)[4] = *reinterpret_cast<float (*)[4]>(&o[4]);
  o0[0] *= a0; o0[1] *= a0; o1[0] *= a0; o1[1] *= a0;
  o0[2] *= a1; o0[3] *= a1; o1[2] *= a1; o1[3] *= a1;
  const uint32_t voff = (uint32_t)(((lane >> 3) & 1) * 256 + (lane >> 4) * 128 + (lane & 7) * 16);
#pragma unroll
  for (int kk = 0; kk < 8; kk++) {
    uint32_t b0, b1, b2, b3;
    ldsm_x4_t(b0, b1, b2, b3, vaddr + kk * 512 + voff);
    mma16816(o0, p[4 * kk], p[4 * kk + 1], p[4 * kk + 2], p[4 * kk + 3], b0, b1);
    mma16816(o1, p[4 * kk], p[4 * kk + 1], p[4 * kk + 2], p[4 * kk + 3], b2, b3);
  }
}

__device__ __forceinline__ void load_q(uint32_t (&q)[4], const bf16* qbase, int t, int lane) {
  const int off = (t >> 3) * 128 + (t & 7) * 8 + (lane & 3) * 2;
  q[0] = *reinterpret_cast<const uint32_t*>(qbase + off);
  q[1] = *reinterpret_cast<const uint32_t*>(qbase + off + 128);
  q[2] = *reinterpret_cast<const uint32_t*>(qbase + off + 64);
  q[3] = *reinterpret_cast<const uint32_t*>(qbase + off + 192);
}

__device__ __forceinline__ void store_o(const float (&o)[8], float l0, float l1, int br, int head, int t, int lane) {
  l0 += __shfl_xor_sync(0xffffffffu, l0, 1);
  l1 += __shfl_xor_sync(0xffffffffu, l1, 1);
  l0 += __shfl_xor_sync(0xffffffffu, l0, 2);
  l1 += __shfl_xor_sync(0xffffffffu, l1, 2);
  const float i0 = 1.f / l0, i1 = 1.f / l1;
  bf16* dst = g_o + (size_t)t * 1024 + br * 512 + head * 16 + (lane & 3) * 2;
  *reinterpret_cast<uint32_t*>(dst) = pack_bf16(o[0] * i0, o[1] * i0);
  *reinterpret_cast<uint32_t*>(dst + 8) = pack_bf16(o[4] * i0, o[5] * i0);
  *reinterpret_cast<uint32_t*>(dst + 8 * 1024) = pack_bf16(o[2] * i1, o[3] * i1);
  *reinterpret_cast<uint32_t*>(dst + 8 * 1024 + 8) = pack_bf16(o[6] * i1, o[7] * i1);
}

__global__ void __launch_bounds__(512, 1) attn_kernel() {
  extern __shared__ uint8_t smem_raw[];
  const uint32_t sbase = (smem_u32(smem_raw) + 1023u) & ~1023u;
  const uint32_t kb_base = sbase, vb_base = sbase + 65536;
  const uint32_t ka_base = sbase + 131072, va_base = ka_base + 6 * 4096;
  const uint32_t bar_base = va_base + 6 * 4096;
  const uint32_t zaddr = bar_base + 8 * 24;
  const int tid = threadIdx.x, warp = tid >> 5, lane = tid & 31, wg = warp >> 2;
  const int head = blockIdx.x >> 2, qblk = blockIdx.x & 3;

  const bf16* qA = g_qkv + (size_t)((0 * 3 + 0) * NH + head) * (SEQ * 16);
  const bf16* kA = g_qkv + (size_t)((0 * 3 + 1) * NH + head) * (SEQ * 16);
  const bf16* vA = g_qkv + (size_t)((0 * 3 + 2) * NH + head) * (SEQ * 16);
  const bf16* qB = g_qkv + (size_t)((1 * 3 + 0) * NH + head) * (SEQ * 16);
  const bf16* kB = g_qkv + (size_t)((1 * 3 + 1) * NH + head) * (SEQ * 16);
  const bf16* vB = g_qkv + (size_t)((1 * 3 + 2) * NH + head) * (SEQ * 16);
  const int ca0 = qblk * 4 - 2;

  if (tid == 0) {
    for (int i = 0; i < 22; i++) mbar_init(bar_base + 8 * i, 1);
    asm volatile("st.shared.f32 [%0], %1;" ::"r"(zaddr), "f"(0.f) : "memory");
    fence_bar_init();
  }
  __syncthreads();
  if (tid == 0) {
    for (int c = 0; c < 16; c++) {
      const uint32_t b = bar_base + 8 * c;
      mbar_expect_tx(b, 8192);
      bulk_load_1d(kb_base + c * 4096, kB + c * 2048, 4096, b);
      bulk_load_1d(vb_base + c * 4096, vB + c * 2048, 4096, b);
    }
    for (int i = 0; i < 6; i++) {
      const int c = ca0 + i;
      if (c >= 0) {
        const uint32_t b = bar_base + 8 * (16 + i);
        mbar_expect_tx(b, 8192);
        bulk_load_1d(ka_base + i * 4096, kA + c * 2048, 4096, b);
        bulk_load_1d(va_base + i * 4096, vA + c * 2048, 4096, b);
      }
    }
  }

  const int rsub = (warp & 3) * 16 + (lane >> 2);
  for (int h2 = 0; h2 < 2; h2++) {
    const int qt = qblk * 512 + wg * 128 + h2 * 64;
    uint32_t q[4];
    load_q(q, qB, qt + rsub, lane);
    float o[8], m0 = -1e30f, m1 = -1e30f, l0 = 0.f, l1 = 0.f;
#pragma unroll
    for (int i = 0; i < 8; i++) o[i] = 0.f;
    for (int c = 0; c < 16; c++) {
      mbar_wait(bar_base + 8 * c, 0);
      attn_tile<false>(o, m0, m1, l0, l1, q, kb_base + c * 4096, vb_base + c * 4096, 0, 0, lane);
    }
    store_o(o, l0, l1, 1, head, qt + rsub, lane);
  }
  for (int h2 = 0; h2 < 2; h2++) {
    const int qt = qblk * 512 + wg * 128 + h2 * 64;
    uint32_t q[4];
    load_q(q, qA, qt + rsub, lane);
    float o[8], m0 = -1e30f, m1 = -1e30f, l0 = 0.f, l1 = 0.f;
#pragma unroll
    for (int i = 0; i < 8; i++) o[i] = 0.f;
    int cfirst = (qt - 255) >> 7;
    if (cfirst < 0) cfirst = 0;
    const int clast = (qt + 63) >> 7;
    for (int c = clast - 2; c <= clast; c++) {
      if (c < cfirst) continue;
      const int i = c - ca0;
      mbar_wait(bar_base + 8 * (16 + i), 0);
      attn_tile<true>(o, m0, m1, l0, l1, q, ka_base + i * 4096, va_base + i * 4096, qt + rsub,
                      c * 128 + (lane & 3) * 2, lane);
    }
    store_o(o, l0, l1, 0, head, qt + rsub, lane);
  }
}

constexpr int G2_STAGES = 4;
constexpr int G2_A_BYTES = 128 * 64 * 2;
constexpr int G2_B_BYTES = 64 * 64 * 2;
constexpr int G2_SMEM = G2_STAGES * (G2_A_BYTES + G2_B_BYTES) + 1024 + 256;

__global__ void __launch_bounds__(288, 1)
gemm_out_kernel(const __grid_constant__ CUtensorMap map_o, const __grid_constant__ CUtensorMap map_woa,
                const __grid_constant__ CUtensorMap map_wob, bf16* __restrict__ out) {
  extern __shared__ uint8_t smem_raw[];
  const uint32_t sbase = (smem_u32(smem_raw) + 1023u) & ~1023u;
  const uint32_t a_base = sbase, b_base = sbase + G2_STAGES * G2_A_BYTES;
  const uint32_t bar_base = b_base + G2_STAGES * G2_B_BYTES;
  const int tid = threadIdx.x, warp = tid >> 5, lane = tid & 31;
  const int mblk = blockIdx.x & 15, nblk = blockIdx.x >> 4;

  if (tid == 0) {
    for (int s = 0; s < G2_STAGES; s++) {
      mbar_init(bar_base + 8 * s, 1);
      mbar_init(bar_base + 8 * (G2_STAGES + s), 8);
    }
    fence_bar_init();
  }
  __syncthreads();

  if (warp == 8) {
    if (lane == 0) {
      for (int it = 0; it < 16; it++) {
        const int s = it & 3;
        const uint32_t ph = (it >> 2) & 1;
        mbar_wait(bar_base + 8 * (G2_STAGES + s), ph ^ 1);
        const uint32_t fb = bar_base + 8 * s;
        mbar_expect_tx(fb, G2_A_BYTES + G2_B_BYTES);
        tma_load_2d(a_base + s * G2_A_BYTES, &map_o, it * 64, mblk * 128, fb);
        tma_load_2d(b_base + s * G2_B_BYTES, (it < 8) ? &map_woa : &map_wob, nblk * 64, (it & 7) * 64, fb);
      }
    }
  } else {
    const int wg = warp >> 2;
    float acc_a[32], acc_b[32];
    for (int it = 0; it < 8; it++) {
      const int s = it & 3;
      const uint32_t ph = (it >> 2) & 1;
      mbar_wait(bar_base + 8 * s, ph);
      wgmma_fence();
#pragma unroll
      for (int kk = 0; kk < 4; kk++) {
        const uint64_t da = make_desc(a_base + s * G2_A_BYTES + wg * 8192 + kk * 32, 16, 1024, 1);
        const uint64_t db = make_desc(b_base + s * G2_B_BYTES + kk * 2048, 8192, 1024, 1);
        wgmma_m64n64k16_ss_tb(acc_a, da, db, (it | kk) != 0);
      }
      wgmma_commit();
      if (it > 0) {
        wgmma_wait<1>();
        if (lane == 0) mbar_arrive(bar_base + 8 * (G2_STAGES + ((it - 1) & 3)));
      }
    }
    for (int it = 8; it < 16; it++) {
      const int s = it & 3;
      const uint32_t ph = (it >> 2) & 1;
      mbar_wait(bar_base + 8 * s, ph);
      wgmma_fence();
#pragma unroll
      for (int kk = 0; kk < 4; kk++) {
        const uint64_t da = make_desc(a_base + s * G2_A_BYTES + wg * 8192 + kk * 32, 16, 1024, 1);
        const uint64_t db = make_desc(b_base + s * G2_B_BYTES + kk * 2048, 8192, 1024, 1);
        wgmma_m64n64k16_ss_tb(acc_b, da, db, ((it & 7) | kk) != 0);
      }
      wgmma_commit();
      wgmma_wait<1>();
      if (lane == 0) mbar_arrive(bar_base + 8 * (G2_STAGES + ((it - 1) & 3)));
    }
    wgmma_wait<0>();
    const int t = mblk * 128 + wg * 64 + (warp & 3) * 16 + (lane >> 2);
    const float g0 = g_gate[t], g1 = g_gate[t + 8];
    const float h0 = bf16_round(1.f - g0), h1 = bf16_round(1.f - g1);
#pragma unroll
    for (int j = 0; j < 8; j++) {
      const int col = nblk * 64 + j * 8 + (lane & 3) * 2;
      *reinterpret_cast<uint32_t*>(out + (size_t)t * DM + col) =
          pack_bf16(g0 * acc_a[4 * j] + h0 * acc_b[4 * j], g0 * acc_a[4 * j + 1] + h0 * acc_b[4 * j + 1]);
      *reinterpret_cast<uint32_t*>(out + (size_t)(t + 8) * DM + col) =
          pack_bf16(g1 * acc_a[4 * j + 2] + h1 * acc_b[4 * j + 2], g1 * acc_a[4 * j + 3] + h1 * acc_b[4 * j + 3]);
    }
  }
}

typedef CUresult (*EncodeFn)(CUtensorMap*, CUtensorMapDataType, cuuint32_t, void*, const cuuint64_t*,
                             const cuuint64_t*, const cuuint32_t*, const cuuint32_t*, CUtensorMapInterleave,
                             CUtensorMapSwizzle, CUtensorMapL2promotion, CUtensorMapFloatOOBfill);

static void encode_2d(EncodeFn fn, CUtensorMap* m, const void* ptr, uint64_t inner, uint64_t outer, uint32_t box_in,
                      uint32_t box_out) {
  cuuint64_t dims[2] = {inner, outer};
  cuuint64_t strides[1] = {inner * 2};
  cuuint32_t box[2] = {box_in, box_out};
  cuuint32_t es[2] = {1, 1};
  fn(m, CU_TENSOR_MAP_DATA_TYPE_BFLOAT16, 2, const_cast<void*>(ptr), dims, strides, box, es,
     CU_TENSOR_MAP_INTERLEAVE_NONE, CU_TENSOR_MAP_SWIZZLE_128B, CU_TENSOR_MAP_L2_PROMOTION_L2_128B,
     CU_TENSOR_MAP_FLOAT_OOB_FILL_NONE);
}

extern "C" void kernel_launch(void* const* d_in, const int* in_sizes, int n_in, void* d_out, int out_size) {
  const bf16* x = (const bf16*)d_in[0];
  const bf16* wqkv_a = (const bf16*)d_in[1];
  const bf16* wo_a = (const bf16*)d_in[2];
  const bf16* wqkv_b = (const bf16*)d_in[4];
  const bf16* wo_b = (const bf16*)d_in[5];
  const bf16* gate_w = (const bf16*)d_in[6];
  bf16* out = (bf16*)d_out;

  EncodeFn enc = nullptr;
  cudaDriverEntryPointQueryResult qres;
  cudaGetDriverEntryPoint("cuTensorMapEncodeTiled", (void**)&enc, cudaEnableDefault, &qres);
  void* o_ptr = nullptr;
  cudaGetSymbolAddress(&o_ptr, g_o);

  CUtensorMap map_x, map_wa, map_wb, map_o, map_woa, map_wob;
  encode_2d(enc, &map_x, x, 512, 2048, 64, 128);
  encode_2d(enc, &map_wa, wqkv_a, 1536, 512, 64, 64);
  encode_2d(enc, &map_wb, wqkv_b, 1536, 512, 64, 64);
  encode_2d(enc, &map_o, o_ptr, 1024, 2048, 64, 128);
  encode_2d(enc, &map_woa, wo_a, 512, 512, 64, 64);
  encode_2d(enc, &map_wob, wo_b, 512, 512, 64, 64);

  cudaFuncSetAttribute(gemm_qkv_kernel, cudaFuncAttributeMaxDynamicSharedMemorySize, G1_SMEM);
  cudaFuncSetAttribute(attn_kernel, cudaFuncAttributeMaxDynamicSharedMemorySize, AT_SMEM);
  cudaFuncSetAttribute(gemm_out_kernel, cudaFuncAttributeMaxDynamicSharedMemorySize, G2_SMEM);

  gemm_qkv_kernel<<<128, 512, G1_SMEM>>>(map_x, map_wa, map_wb, x, gate_w);
  attn_kernel<<<128, 512, AT_SMEM>>>();
  gemm_out_kernel<<<128, 288, G2_SMEM>>>(map_o, map_woa, map_wob, out);
}
```
